```python
import torch

def _softmax(x, axis=-1):
    return torch.softmax(x, dim=axis)
def _gelu(x):
    return torch.nn.functional.gelu(x, approximate="tanh")
def _silu(x):
    return torch.nn.functional.silu(x)
def _sigmoid(x):
    return torch.sigmoid(x)
def _layernorm(x, axis=-1, eps=1e-5):
    m = x.mean(dim=axis, keepdim=True)
    v = x.var(dim=axis, keepdim=True, unbiased=False)
    return (x - m) / torch.sqrt(v + eps)
def _scatter_add(tgt, idx, src, axis=0):
    return tgt.clone().index_add_(axis, idx, src)
def _segment_sum(src, seg, n):
    out = torch.zeros((n,) + src.shape[1:], dtype=src.dtype)
    return out.index_add_(0, seg, src)
def _pad(x, pw):
    flat = tuple(v for pair in reversed(pw) for v in pair)
    return torch.nn.functional.pad(x, flat)

kernel_name = 'gated_mix__mha_block_cached__glu_gated_reglu__decode'

def setup_inputs():

    _w = (lambda a: (lambda t: t.to(torch.bfloat16) if t.is_floating_point() else t)(torch.as_tensor(a)))
    def _A_setup():
        B, Sq, D = 2, 1, 448
        H, Sk, Dh = 16, 4096, 256
        return {
            "x": _w((lambda *s: torch.randn(*s, dtype=torch.bfloat16) * 0.05)(B, Sq, D)),
            "k_cache": _w((lambda *s: torch.randn(*s, dtype=torch.bfloat16) * 3.2)(B, H, Sk, Dh)),
            "v_cache": _w((lambda *s: torch.randn(*s, dtype=torch.bfloat16) * 0.05)(B, H, Sk, Dh)),
            "wq": _w((lambda *s: torch.randn(*s, dtype=torch.bfloat16) * 3.2)(D, H * Dh) * (D ** -0.5)),
            "wo": _w((lambda *s: torch.randn(*s, dtype=torch.bfloat16) * 0.05)(H * Dh, D) * ((H * Dh) ** -0.5)),
        }
    _A_in = _A_setup()

    def _B_setup():
        B, S, D, F = 2, 1, 448, 1792
        return {
            "x": _w((lambda *s: torch.randn(*s, dtype=torch.bfloat16) * 0.05)(B, S, D)),
            "W_gate": _w((lambda *s: torch.randn(*s, dtype=torch.bfloat16) * 0.2)(D, F) * (2.0 / D) ** 0.5),
            "W_up": _w((lambda *s: torch.randn(*s, dtype=torch.bfloat16) * 0.2)(D, F) * (2.0 / D) ** 0.5),
            "W_down": _w((lambda *s: torch.randn(*s, dtype=torch.bfloat16) * 0.2)(F, D) * (1.0 / F) ** 0.5),
        }
    _B_in = _B_setup()

    return {
        "A_x": _A_in["x"],
        "A_k_cache": _A_in["k_cache"],
        "A_v_cache": _A_in["v_cache"],
        "A_wq": _A_in["wq"],
        "A_wo": _A_in["wo"],
        "B_x": _B_in["x"],
        "B_W_gate": _B_in["W_gate"],
        "B_W_up": _B_in["W_up"],
        "B_W_down": _B_in["W_down"],
        "gate_w": _w((lambda *s: torch.randn(*s, dtype=torch.bfloat16) * 0.05)(448) * 16.0),
    }

def reference(A_x, A_k_cache, A_v_cache, A_wq, A_wo, B_x, B_W_gate, B_W_up, B_W_down, gate_w):
    def _A_ref(x, k_cache, v_cache, wq, wo):
        B, Sq, D = x.shape
        H, Dh = 16, 256
        q = (lambda x, *d: x.permute(*d))((x @ wq).reshape(B, Sq, H, Dh), 0, 2, 1, 3)
        scores = torch.einsum("bhqd,bhkd->bhqk", q, k_cache) * (Dh ** -0.5)
        p = _softmax(scores, axis=-1)
        o = torch.einsum("bhqk,bhkd->bhqd", p, v_cache)
        return (lambda x, *d: x.permute(*d))(o, 0, 2, 1, 3).reshape(B, Sq, H * Dh) @ wo

    def _B_ref(x, W_gate, W_up, W_down):
        gate = torch.einsum("bsd,df->bsf", x, W_gate)
        up = torch.einsum("bsd,df->bsf", x, W_up)
        gate = gate * (lambda x, dt: x.to(dt))(gate > 0, gate.dtype)
        h = gate * up
        return torch.einsum("bsf,fd->bsd", h, W_down)

    x = A_x
    g = _sigmoid((x * gate_w).sum(-1, keepdims=True))
    a = _A_ref(x, A_k_cache, A_v_cache, A_wq, A_wo)
    b = _B_ref(x, B_W_gate, B_W_up, B_W_down)
    return g * a + (1 - g) * b
```

```cpp
#include <cuda_runtime.h>
#include <cuda_bf16.h>
#include <stdint.h>

namespace {

constexpr int DM    = 448;
constexpr int NH    = 16;
constexpr int SK    = 4096;
constexpr int DH    = 256;
constexpr int DFF   = 1792;
constexpr int NCTA  = 128;
constexpr int NW    = 8;
#define P_SLOTS 4
#define P_DEPTH0 1
constexpr int SLOTS  = P_SLOTS;
constexpr int DEPTH0 = P_DEPTH0;
constexpr int TILE_BYTES = 8 * DH * 2;
constexpr int NT    = 16;
constexpr int NTHREADS = (NW + 1) * 32;
constexpr float LOG2E = 1.4426950408889634f;
constexpr float SM_SCALE = 0.0625f * LOG2E;
constexpr unsigned SPIN_LIMIT = 1u << 24;

constexpr int SM_FIFO  = 0;
constexpr int SM_STAGE = SM_FIFO + NW * SLOTS * TILE_BYTES;
constexpr int SM_FRAG  = SM_STAGE + 56 * 512;
constexpr int SM_PW    = SM_FRAG + NW * 12 * 512;
constexpr int SM_QRED  = SM_PW + NW * 144 * 4;
constexpr int SM_QS    = SM_QRED + NW * 128 * 4;
constexpr int SM_XS    = SM_QS + 512;
constexpr int SM_HS    = SM_XS + 3 * DM * 2;
constexpr int SM_ML    = SM_HS + 7 * 32 * 4;
constexpr int SM_FAC   = SM_ML + NW * 8;
constexpr int SM_BAR   = SM_FAC + NW * 4;
constexpr int SM_TOTAL = SM_BAR + (NW * SLOTS + 5) * 8;
static_assert(SM_BAR % 8 == 0, "align");
static_assert(SM_TOTAL <= 232448, "smem");

constexpr int G_QP = 0;
constexpr int G_O1 = G_QP + NCTA * 128;
constexpr int G_O2 = G_O1 + NCTA * 256;
constexpr int G_HH = G_O2 + 112 * NH * 8;
constexpr int G_ST = G_HH + NCTA * 32;
constexpr int G_STATE = G_ST + NCTA * 8;
__device__ __align__(128) unsigned g_scr[G_STATE + 32];

#define MC(v)
#define TL(i)
#define TLW(i)
#define TT(i)
#define TDUMP_W()
#define TDUMP_A()

__device__ __forceinline__ void mbar_init(uint32_t bar, uint32_t cnt) {
    asm volatile("mbarrier.init.shared::cta.b64 [%0], %1;" :: "r"(bar), "r"(cnt) : "memory");
}
__device__ __forceinline__ void mbar_expect_tx(uint32_t bar, uint32_t bytes) {
    asm volatile("mbarrier.arrive.expect_tx.shared::cta.b64 _, [%0], %1;" :: "r"(bar), "r"(bytes) : "memory");
}
__device__ __forceinline__ void mbar_arrive(uint32_t bar) {
    asm volatile("mbarrier.arrive.shared::cta.b64 _, [%0];" :: "r"(bar) : "memory");
}
__device__ __forceinline__ bool mbar_test(uint32_t bar, uint32_t parity) {
    uint32_t ok;
    asm volatile("{\n.reg .pred p;\nmbarrier.test_wait.parity.shared::cta.b64 p, [%1], %2;\nselp.u32 %0, 1, 0, p;\n}"
                 : "=r"(ok) : "r"(bar), "r"(parity) : "memory");
    return ok;
}
__device__ __forceinline__ void mbar_wait(uint32_t bar, uint32_t parity) {
    asm volatile("{\n.reg .pred p, q;\n.reg .u32 n;\nmov.u32 n, 0;\n"
                 "WAIT_LOOP:\nmbarrier.try_wait.parity.shared::cta.b64 p, [%0], %1;\n@p bra WAIT_DONE;\n"
                 "add.u32 n, n, 1;\nsetp.lt.u32 q, n, %2;\n@q bra WAIT_LOOP;\ntrap;\nWAIT_DONE:\n}"
                 :: "r"(bar), "r"(parity), "n"(SPIN_LIMIT) : "memory");
}
__device__ __forceinline__ void bulk_g2s(uint32_t dst, const void* src, uint32_t bar, uint64_t pol) {
    asm volatile("cp.async.bulk.shared::cluster.global.mbarrier::complete_tx::bytes.L2::cache_hint [%0], [%1], %2, [%3], %4;"
                 :: "r"(dst), "l"(src), "n"(TILE_BYTES), "r"(bar), "l"(pol) : "memory");
}
__device__ __forceinline__ uint64_t stream_policy() {
    uint64_t pol;
    asm volatile("createpolicy.fractional.L2::evict_first.b64 %0, 1.0;" : "=l"(pol));
    return pol;
}
__device__ __forceinline__ void cp16(uint32_t dst, const void* src) {
    asm volatile("cp.async.cg.shared.global [%0], [%1], 16;" :: "r"(dst), "l"(src) : "memory");
}
__device__ __forceinline__ uint4 ldg128(const void* p) {
    uint4 v;
    asm volatile("ld.global.nc.L1::no_allocate.v4.u32 {%0,%1,%2,%3}, [%4];" : "=r"(v.x), "=r"(v.y), "=r"(v.z), "=r"(v.w) : "l"(p));
    return v;
}
__device__ __forceinline__ unsigned ldg_u16(const __nv_bfloat16* p) {
    unsigned short v; asm volatile("ld.global.nc.u16 %0, [%1];" : "=h"(v) : "l"(p)); return v;
}
__device__ __forceinline__ uint4 lds128(uint32_t a) {
    uint4 v;
    asm volatile("ld.shared.v4.u32 {%0,%1,%2,%3}, [%4];" : "=r"(v.x), "=r"(v.y), "=r"(v.z), "=r"(v.w) : "r"(a) : "memory");
    return v;
}
__device__ __forceinline__ uint2 lds64(uint32_t a) {
    uint2 v; asm volatile("ld.shared.v2.u32 {%0,%1}, [%2];" : "=r"(v.x), "=r"(v.y) : "r"(a) : "memory"); return v;
}
__device__ __forceinline__ unsigned lds32(uint32_t a) {
    unsigned v; asm volatile("ld.shared.u32 %0, [%1];" : "=r"(v) : "r"(a) : "memory"); return v;
}
__device__ __forceinline__ unsigned lds16(uint32_t a) {
    unsigned short v; asm volatile("ld.shared.u16 %0, [%1];" : "=h"(v) : "r"(a) : "memory"); return v;
}
__device__ __forceinline__ void sts128f(uint32_t a, float x, float y, float z, float w) {
    asm volatile("st.shared.v4.f32 [%0], {%1,%2,%3,%4};" :: "r"(a), "f"(x), "f"(y), "f"(z), "f"(w) : "memory");
}
__device__ __forceinline__ void sts64f(uint32_t a, float x, float y) {
    asm volatile("st.shared.v2.f32 [%0], {%1,%2};" :: "r"(a), "f"(x), "f"(y) : "memory");
}
__device__ __forceinline__ void sts32(uint32_t a, unsigned v) { asm volatile("st.shared.u32 [%0], %1;" :: "r"(a), "r"(v) : "memory"); }
__device__ __forceinline__ void sts16(uint32_t a, unsigned v) { asm volatile("st.shared.u16 [%0], %1;" :: "r"(a), "h"((unsigned short)v) : "memory"); }
__device__ __forceinline__ unsigned ld_rlx(const unsigned* p) {
    unsigned v; asm volatile("ld.relaxed.gpu.global.u32 %0, [%1];" : "=r"(v) : "l"(p) : "memory"); return v;
}
__device__ __forceinline__ uint2 ld_rlx2(const unsigned* p) {
    uint2 v; asm volatile("ld.relaxed.gpu.global.v2.u32 {%0,%1}, [%2];" : "=r"(v.x), "=r"(v.y) : "l"(p) : "memory"); return v;
}
__device__ __forceinline__ uint4 ld_rlx4(const unsigned* p) {
    uint4 v; asm volatile("ld.relaxed.gpu.global.v4.u32 {%0,%1,%2,%3}, [%4];" : "=r"(v.x), "=r"(v.y), "=r"(v.z), "=r"(v.w) : "l"(p) : "memory"); return v;
}
__device__ __forceinline__ void st_rlx(unsigned* p, unsigned v) {
    asm volatile("st.relaxed.gpu.global.u32 [%0], %1;" :: "l"(p), "r"(v) : "memory");
}
__device__ __forceinline__ void st_rlx4(unsigned* p, unsigned a, unsigned b, unsigned c, unsigned d) {
    asm volatile("st.relaxed.gpu.global.v4.u32 [%0], {%1,%2,%3,%4};" :: "l"(p), "r"(a), "r"(b), "r"(c), "r"(d) : "memory");
}
__device__ __forceinline__ unsigned tagw(float v, unsigned tag) { return (__float_as_uint(v) & ~3u) | tag; }
__device__ __forceinline__ float untag(unsigned w) { return __uint_as_float(w & ~3u); }
__device__ __forceinline__ unsigned tag_bad(unsigned w, unsigned tag) { return (w ^ tag) & 3u; }
__device__ __forceinline__ void spin_check(unsigned& n) { if (++n > SPIN_LIMIT) __trap(); }
__device__ __forceinline__ unsigned bf_bits(float v) { return (unsigned)__bfloat16_as_ushort(__float2bfloat16_rn(v)); }
__device__ __forceinline__ float as_f(unsigned v) { return __uint_as_float(v); }
__device__ __forceinline__ float ex2(float v) { float r; asm("ex2.approx.ftz.f32 %0, %1;" : "=f"(r) : "f"(v)); return r; }
__device__ __forceinline__ float rcp(float v) { float r; asm("rcp.approx.ftz.f32 %0, %1;" : "=f"(r) : "f"(v)); return r; }
__device__ __forceinline__ void mma16816(float (&c)[4], unsigned a0, unsigned a1, unsigned a2, unsigned a3, unsigned b0, unsigned b1) {
    asm volatile("mma.sync.aligned.m16n8k16.row.col.f32.bf16.bf16.f32 {%0,%1,%2,%3}, {%4,%5,%6,%7}, {%8,%9}, {%0,%1,%2,%3};"
                 : "+f"(c[0]), "+f"(c[1]), "+f"(c[2]), "+f"(c[3]) : "r"(a0), "r"(a1), "r"(a2), "r"(a3), "r"(b0), "r"(b1));
}
__device__ __forceinline__ void mma16816(float (&c)[4], const uint4& a, unsigned b0, unsigned b1) { mma16816(c, a.x, a.y, a.z, a.w, b0, b1); }
__device__ __forceinline__ bool elect_one() {
    uint32_t p;
    asm volatile("{\n.reg .pred p;\nelect.sync _|p, 0xffffffff;\nselp.u32 %0, 1, 0, p;\n}" : "=r"(p));
    return p;
}
__device__ __forceinline__ void bar_sync(int id, int n)   { asm volatile("bar.sync %0, %1;" :: "r"(id), "r"(n) : "memory"); }
__device__ __forceinline__ void bar_arrive(int id, int n) { asm volatile("bar.arrive %0, %1;" :: "r"(id), "r"(n) : "memory"); }

__global__ void __launch_bounds__(NTHREADS, 1)
fused_decode_kernel(const __nv_bfloat16* __restrict__ x, const __nv_bfloat16* __restrict__ Kc, const __nv_bfloat16* __restrict__ Vc,
                    const __nv_bfloat16* __restrict__ wq, const __nv_bfloat16* __restrict__ wo,
                    const __nv_bfloat16* __restrict__ Wg, const __nv_bfloat16* __restrict__ Wu, const __nv_bfloat16* __restrict__ Wd,
                    const __nv_bfloat16* __restrict__ gate_w, __nv_bfloat16* __restrict__ out)
{
    extern __shared__ __align__(128) unsigned char smem[];
    uint32_t sb;
    asm volatile("mov.u32 %0, %1;" : "=r"(sb) : "r"((uint32_t)__cvta_generic_to_shared(smem)));
    unsigned* scr;
    asm volatile("mov.u64 %0, %1;" : "=l"(scr) : "l"(g_scr));
    const int c = blockIdx.x, h = c >> 3, r = c & 7, b = r >> 2, s = r & 3;
    const int warp = __shfl_sync(~0u, (int)(threadIdx.x >> 5), 0), lane = threadIdx.x & 31, g = lane >> 2, t = lane & 3;
    const uint32_t bar_ml  = sb + SM_BAR + NW * SLOTS * 8;
    const uint32_t bar_hs  = bar_ml + 8;
    const uint32_t bar_fac = bar_ml + 16;
    const uint32_t bar_q   = bar_ml + 24;
    const uint32_t bar_w   = bar_ml + 32;
    const int bb = (g >> 1) & 1;
    const unsigned mulp = (g & 1) ? 65536u : 1u;
    const unsigned mul0 = (g & 4) ? 0u : mulp, mul1 = (g & 4) ? mulp : 0u;

    if (warp < NW) {
        TLW(0);
        const uint32_t fifo = sb + SM_FIFO + warp * SLOTS * TILE_BYTES;
        const uint32_t fbar = sb + SM_BAR + warp * SLOTS * 8;
        if (lane == 0) {
#pragma unroll
            for (int i = 0; i < SLOTS; i++) mbar_init(fbar + i * 8, 1);
            asm volatile("fence.mbarrier_init.release.cluster;" ::: "memory");
            asm volatile("fence.proxy.async.shared::cta;" ::: "memory");
        }
        unsigned xb[7];
        uint4 wv[7];
        {
            const int row = 224 * (r & 1) + 28 * warp + t;
            const __nv_bfloat16* xp = x + bb * DM + row;
            const __nv_bfloat16* wp = wq + (size_t)row * (NH * DH) + 256 * h + 64 * (r >> 1) + 8 * g;
#pragma unroll
            for (int j = 0; j < 7; j++) xb[j] = ldg_u16(xp + 4 * j);
#pragma unroll
            for (int j = 0; j < 7; j++) {
                wv[j] = ldg128(wp + (size_t)(4 * j) * (NH * DH));
            }
        }
        const unsigned state = ld_rlx(scr + G_STATE);
        unsigned* const qp_out = scr + G_QP + c * 128 + threadIdx.x;
        unsigned* const o1_out = scr + G_O1 + c * 256 + threadIdx.x;
        unsigned* const o2_out = scr + G_O2 + (((t & 1) * 56 + 7 * r + g) * NH + h) * 8 + 4 * (t >> 1);
        if (warp < 4) st_rlx(qp_out, 0u);
        st_rlx(o1_out, 0u);
        if (warp == 0 && g < 7) st_rlx4(o2_out, 0u, 0u, 0u, 0u);

        const size_t kv_off = ((size_t)(b * NH + h) * SK + s * 1024 + warp * 8) * DH;
        const unsigned char* const vbase = reinterpret_cast<const unsigned char*>(Vc + kv_off);
        const unsigned char* nsrc = reinterpret_cast<const unsigned char*>(Kc + kv_off);
        const uint64_t pol = stream_policy();
        auto issue = [&](int slot) {
            mbar_expect_tx(fbar + slot * 8, TILE_BYTES);
            bulk_g2s(fifo + slot * TILE_BYTES, nsrc, fbar + slot * 8, pol);
        };
        nsrc += __shfl_sync(~0u, wv[0].x, lane) ^ wv[0].x;
#pragma unroll
        for (int i = 0; i < SLOTS; i++) {
            if (i < DEPTH0 && elect_one()) issue(i);
            nsrc += NW * TILE_BYTES;
        }
        bar_arrive(3, NTHREADS);

        const unsigned tag = state == 3u ? 1u : state + 1u;
        {
            float c0[4] = {0.f, 0.f, 0.f, 0.f}, c1[4] = {0.f, 0.f, 0.f, 0.f};
#pragma unroll
            for (int j = 0; j < 7; j++) mma16816((j & 1) ? c1 : c0, wv[j], xb[j] * mul0, xb[j] * mul1);
            sts128f(sb + SM_QRED + (warp * 128 + (t & 1) * 64 + 8 * g + 4 * (t >> 1)) * 4, c0[0] + c1[0], c0[1] + c1[1], c0[2] + c1[2], c0[3] + c1[3]);
        }
        bar_sync(4, NW * 32);
        if (warp < 4) {
            const uint32_t qr = sb + SM_QRED + threadIdx.x * 4;
            float v = 0.f;
#pragma unroll
            for (int w = 0; w < NW; w++) v += as_f(lds32(qr + w * 512));
            st_rlx(qp_out, tagw(v, tag));
        }
        TLW(1);
        {
            const unsigned* qp = scr + G_QP + (h * 8 + (warp & 6)) * 128 + b * 64 + (warp & 1) * 32 + lane;
            unsigned w0, w1, n = 0;
            do { w0 = ld_rlx(qp); w1 = ld_rlx(qp + 128); spin_check(n); } while (__any_sync(~0u, tag_bad(w0, tag) | tag_bad(w1, tag)));
            const int k = (lane >> 1) & 3;
            sts16(sb + SM_QS + (4 * warp + (lane >> 3)) * 16 + ((k & 1) * 2 + (k >> 1)) * 4 + (lane & 1) * 2, bf_bits(untag(w0) + untag(w1)));
        }
        bar_sync(1, NTHREADS);
        TLW(2);
        if (threadIdx.x == 0) mbar_arrive(bar_q);
        uint2 qf[8];
#pragma unroll
        for (int j = 0; j < 8; j++) qf[j] = lds64(sb + SM_QS + (t + 4 * (j ^ (g & 1))) * 16 + bb * 8);

        float s0 = 0.f, s1 = 0.f, s2 = 0.f, s3 = 0.f;
        int slot = 0; uint32_t phase = 0;
#pragma unroll 1
        for (int it = 0; it < NT; it++) {
            mbar_wait(fbar + slot * 8, phase);
            TT(it);
            const uint32_t tile = fifo + slot * TILE_BYTES + g * 512 + t * 16;
            float c0[4] = {0.f, 0.f, 0.f, 0.f}, c1[4] = {0.f, 0.f, 0.f, 0.f};
#pragma unroll
            for (int j = 0; j < 8; j += 2) {
                const uint4 X0 = lds128(tile + 64 * j + 64 * (g & 1)), X1 = lds128(tile + 64 * (j + 1) - 64 * (g & 1));
                mma16816(c0, X0, qf[j].x, qf[j].y);
                mma16816(c1, X1, qf[j + 1].x, qf[j + 1].y);
            }
            __syncwarp();
            if (it + SLOTS == NT) nsrc = vbase;
            if (elect_one()) issue(slot);
            nsrc += NW * TILE_BYTES;
            asm volatile("" : "+l"(nsrc));
            const float v = (t & 1) ? ((g & 1) ? c0[3] + c1[3] : c0[2] + c1[2]) : ((g & 1) ? c0[1] + c1[1] : c0[0] + c1[0]);
            const float sc = v + __shfl_xor_sync(~0u, v, 1);
            if ((it & 3) == t) {
                if (it < 4) s0 = sc; else if (it < 8) s1 = sc; else if (it < 12) s2 = sc; else s3 = sc;
            }
            if (++slot == SLOTS) { slot = 0; phase ^= 1; }
        }
        TLW(3);
        const uint32_t pw = sb + SM_PW + warp * 144 * 4;
        {
            float m = fmaxf(fmaxf(s0, s1), fmaxf(s2, s3));
#pragma unroll
            for (int o = 16; o > 0; o >>= 1) m = fmaxf(m, __shfl_xor_sync(~0u, m, o));
            const float p0 = ex2((s0 - m) * SM_SCALE), p1 = ex2((s1 - m) * SM_SCALE);
            const float p2 = ex2((s2 - m) * SM_SCALE), p3 = ex2((s3 - m) * SM_SCALE);
            float l = (p0 + p1) + (p2 + p3);
#pragma unroll
            for (int o = 16; o > 0; o >>= 1) l += __shfl_xor_sync(~0u, l, o);
            const uint32_t pp = pw + ((g & 3) * 36 + 2 * t + (g >> 2)) * 4;
            sts32(pp, bf_bits(p0)); sts32(pp + 32, bf_bits(p1)); sts32(pp + 64, bf_bits(p2)); sts32(pp + 96, bf_bits(p3));
            if (lane == 0) {
                sts64f(sb + SM_ML + warp * 8, m, l);
                mbar_arrive(bar_ml);
            }
            __syncwarp();
        }
        float acc[4][2][4];
#pragma unroll
        for (int i = 0; i < 4; i++)
#pragma unroll
            for (int j = 0; j < 2; j++)
#pragma unroll
                for (int k = 0; k < 4; k++) acc[i][j][k] = 0.f;
        const unsigned mulv = ((g >> 1) == t) ? mulp : 0u;
        float C0[4] = {0.f, 0.f, 0.f, 0.f}, C1[4] = {0.f, 0.f, 0.f, 0.f};
        const uint32_t frag = sb + SM_FRAG + warp * 12 * 512 + lane * 16;
#pragma unroll 1
        for (int iv = 0; iv < NT; iv++) {
            mbar_wait(fbar + slot * 8, phase);
            TT(NT + iv);
            const uint2 P = lds64(pw + (t * 36 + 2 * iv) * 4);
            const unsigned B0 = P.x * mulv, B1 = P.y * mulv;
            const uint32_t tile = fifo + slot * TILE_BYTES + t * 512 + (8 * (g >> 1) + (g & 1)) * 16;
#pragma unroll
            for (int rr = 0; rr < 4; rr++) {
                const uint32_t a = tile + 32 * (t ^ rr);
                const uint4 X = lds128(a), Y = lds128(a + 4 * 512);
                mma16816(acc[rr][0], X, B0, 0u);
                mma16816(acc[rr][1], X, 0u, B0);
                mma16816(acc[rr][0], Y, B1, 0u);
                mma16816(acc[rr][1], Y, 0u, B1);
            }
            __syncwarp();
            if (iv + SLOTS < NT && elect_one()) issue(slot);
            nsrc += NW * TILE_BYTES;
            asm volatile("" : "+l"(nsrc));
            if (iv == NT - 2) {
                mbar_wait(bar_w, 0);
                mbar_wait(bar_hs, 0);
                if (warp < 7) {
                    const uint4 Hs = lds128(sb + SM_HS + (warp * 32 + bb * 16 + t * 4) * 4);
                    mma16816(C0, lds128(frag), Hs.x * mul0, Hs.x * mul1);
                    mma16816(C1, lds128(frag + 512), Hs.y * mul0, Hs.y * mul1);
                    mma16816(C0, lds128(frag + 1024), Hs.z * mul0, Hs.z * mul1);
                    mma16816(C1, lds128(frag + 1536), Hs.w * mul0, Hs.w * mul1);
                }
            }
            if (++slot == SLOTS) { slot = 0; phase ^= 1; }
        }
        TLW(4);
        MC(m0);
        mbar_wait(bar_fac, 0);
        const float fac = as_f(lds32(sb + SM_FAC + warp * 4));
        {
            float f[8];
#pragma unroll
            for (int j = 0; j < 2; j++)
#pragma unroll
                for (int k = 0; k < 4; k++)
                    f[4 * j + k] = ((acc[0][j][k] + __shfl_xor_sync(~0u, acc[1][j][k], 1)) +
                                    (__shfl_xor_sync(~0u, acc[2][j][k], 2) + __shfl_xor_sync(~0u, acc[3][j][k], 3))) * fac;
            const uint32_t dst = fifo + (8 * (g >> 1) + 2 * t + (g & 1)) * 32;
            sts128f(dst, f[0], f[1], f[2], f[3]);
            sts128f(dst + 16, f[4], f[5], f[6], f[7]);
        }
        bar_sync(2, NW * 32);
        {
            const uint32_t a = sb + SM_FIFO + threadIdx.x * 4;
            float v[8];
#pragma unroll
            for (int w = 0; w < NW; w++) v[w] = as_f(lds32(a + w * SLOTS * TILE_BYTES));
            st_rlx(o1_out, tagw(((v[0] + v[1]) + (v[2] + v[3])) + ((v[4] + v[5]) + (v[6] + v[7])), tag));
        }
        TLW(5);
        MC(m1);
        uint4 wf[8];
#pragma unroll
        for (int j = 0; j < 8; j++) wf[j] = lds128(frag + (4 + j) * 512);
        unsigned pk;
        {
            const unsigned* op = scr + G_O1 + h * 8 * 256 + threadIdx.x;
            unsigned w[8], pending = 0xffu, n = 0;
            while (true) {
#pragma unroll
                for (int i = 0; i < 8; i++) if (pending >> i & 1) w[i] = ld_rlx(op + i * 256);
#pragma unroll
                for (int i = 0; i < 8; i++) if (!__any_sync(~0u, tag_bad(w[i], tag))) pending &= ~(1u << i);
                if (!pending) break;
                spin_check(n);
            }
            pk = bf_bits((untag(w[0]) + untag(w[1])) + (untag(w[2]) + untag(w[3])))
               | bf_bits((untag(w[4]) + untag(w[5])) + (untag(w[6]) + untag(w[7]))) << 16;
        }
        TLW(6);
        MC(m2);
        {
            const unsigned sel = (g & 1) ? (0x44u | (2 * bb) << 8 | (2 * bb + 1) << 12) : ((2 * bb) | (2 * bb + 1) << 4 | 0x4400u);
            const unsigned sel0 = (g & 4) ? 0x4444u : sel, sel1 = (g & 4) ? sel : 0x4444u;
#pragma unroll
            for (int j = 0; j < 8; j++) {
                const unsigned o = __shfl_sync(~0u, pk, 4 * j + t);
                mma16816((j & 1) ? C1 : C0, wf[j], __byte_perm(o, 0u, sel0), __byte_perm(o, 0u, sel1));
            }
            sts128f(fifo + 2048 + lane * 16, C0[0] + C1[0], C0[1] + C1[1], C0[2] + C1[2], C0[3] + C1[3]);
        }
        bar_sync(2, NW * 32);
        if (warp == 0) {
            float e0 = 0.f, e1 = 0.f, e2 = 0.f, e3 = 0.f;
#pragma unroll
            for (int w = 0; w < NW; w++) {
                const uint4 v = lds128(sb + SM_FIFO + w * SLOTS * TILE_BYTES + 2048 + lane * 16);
                e0 += as_f(v.x); e1 += as_f(v.y); e2 += as_f(v.z); e3 += as_f(v.w);
            }
            if (g < 7) st_rlx4(o2_out, tagw(e0, tag), tagw(e1, tag), tagw(e2, tag), tagw(e3, tag));
        }
        TLW(7);
        TDUMP_W();
    } else {
        if (lane == 0) {
            mbar_init(bar_ml, NW); mbar_init(bar_hs, 1); mbar_init(bar_fac, 1); mbar_init(bar_q, 1); mbar_init(bar_w, 32);
            asm volatile("fence.mbarrier_init.release.cluster;" ::: "memory");
        }
        __syncwarp();
        bar_arrive(1, NTHREADS);
        const unsigned state = ld_rlx(scr + G_STATE);
        bar_sync(3, NTHREADS);
        {
            const int w = lane & (NW - 1);
            const unsigned char* kb = reinterpret_cast<const unsigned char*>(Kc + ((size_t)(b * NH + h) * SK + s * 1024 + w * 8) * DH);
            const uint32_t fb = sb + SM_BAR + w * SLOTS * 8, ff = sb + SM_FIFO + w * SLOTS * TILE_BYTES;
            const uint64_t pol = stream_policy();
            int k = lane < NW ? DEPTH0 : SLOTS;
            unsigned n = 0;
            while (__any_sync(~0u, k < SLOTS)) {
                const bool q_ready = mbar_test(bar_q, 0);
                if (k < SLOTS && (q_ready || mbar_test(fb + (k - DEPTH0) * 8, 0))) {
                    mbar_expect_tx(fb + k * 8, TILE_BYTES);
                    bulk_g2s(ff + k * TILE_BYTES, kb + (size_t)k * (NW * TILE_BYTES), fb + k * 8, pol);
                    k++;
                }
                spin_check(n);
            }
        }
        const unsigned tag = state == 3u ? 1u : state + 1u;
        mbar_wait(bar_q, 0);
        const int set = g >> 2;
        if (r < 7) {
            const __nv_bfloat16* wp = ((g & 2) ? Wu : Wg) + (size_t)(8 * set + t) * DFF + 112 * h + 16 * r + 8 * (g & 1);
#pragma unroll 1
            for (int j = 0; j < 28; j++) {
                cp16(sb + SM_STAGE + j * 1024 + lane * 16, wp);
                cp16(sb + SM_STAGE + j * 1024 + 512 + lane * 16, wp + 4 * DFF);
                wp += 16 * DFF;
            }
        }
#pragma unroll 1
        for (int i = lane; i < 168; i += 32)
            cp16(sb + SM_XS + i * 16, i < 112 ? x + 8 * i : gate_w + 8 * (i - 112));
        asm volatile("cp.async.wait_all;" ::: "memory");
        __syncwarp();
        float g0, g1;
        {
            float c1[4] = {0.f, 0.f, 0.f, 0.f}, c2[4] = {0.f, 0.f, 0.f, 0.f}, cz[4] = {0.f, 0.f, 0.f, 0.f};
            uint32_t wa = sb + SM_STAGE + lane * 16;
            uint32_t xa = sb + SM_XS + (bb * DM + 8 * set + t) * 2;
            uint32_t za = sb + SM_XS + ((g & 1) * DM + 2 * t) * 2;
            uint32_t zb = sb + SM_XS + (2 * DM + 2 * t) * 2;
#pragma unroll 1
            for (int j = 0; j < 28; j++) {
                const uint2 X0 = lds64(wa), Y0 = lds64(wa + 512), X1 = lds64(wa + 8), Y1 = lds64(wa + 520);
                const unsigned B0 = lds16(xa) * mulp, B1 = lds16(xa + 8) * mulp;
                const unsigned a0 = lds32(za), a1 = lds32(za + 16);
                mma16816(c1, X0.x, X0.y, Y0.x, Y0.y, B0, B1);
                mma16816(c2, X1.x, X1.y, Y1.x, Y1.y, B0, B1);
                mma16816(cz, a0, a0, a1, a1, lds32(zb), lds32(zb + 16));
                wa += 1024; xa += 32; za += 32; zb += 32;
            }
            const float gz = rcp(1.f + ex2(-LOG2E * cz[0]));
            g0 = __shfl_sync(~0u, gz, 0);
            g1 = __shfl_sync(~0u, gz, 4);
            const float sc = 1.f - ((t & 1) ? g1 : g0);
            unsigned hw[4];
#pragma unroll
            for (int k = 0; k < 4; k++) {
                const float v = (set ? c2[k] : c1[k]) + __shfl_xor_sync(~0u, set ? c1[k] : c2[k], 18);
                const float u = __shfl_xor_sync(~0u, v, 8);
                hw[k] = tagw((v > 0.f ? v * u : 0.f) * sc, tag);
            }
            if (r < 7 && (t >> 1) == set && !(g & 2))
                st_rlx4(scr + G_HH + c * 32 + (t & 1) * 16 + 8 * (g & 1) + 4 * set, hw[0], hw[1], hw[2], hw[3]);
        }
        TL(8);
        {
            const int gc = g < 7 ? g : 6;
            const __nv_bfloat16* wd = Wd + (size_t)(112 * h + t) * DM + 56 * r + 8 * gc;
            const __nv_bfloat16* wp = wo + (size_t)(256 * h + t) * DM + 56 * r + 8 * gc;
            uint32_t dst = sb + SM_FRAG + lane * 16;
#pragma unroll 1
            for (int w = 0; w < NW; w++) {
                if (w < 7) {
#pragma unroll
                    for (int j = 0; j < 4; j++) cp16(dst + j * 512, wd + 4 * j * DM);
                }
#pragma unroll
                for (int j = 0; j < 8; j++) cp16(dst + (4 + j) * 512, wp + 4 * j * DM);
                dst += 12 * 512; wd += 16 * DM; wp += 32 * DM;
            }
            asm volatile("cp.async.mbarrier.arrive.noinc.shared::cta.b64 [%0];" :: "r"(bar_w) : "memory");
        }
        {
            const unsigned* hp = scr + G_HH + h * 8 * 32 + lane;
            const int f = lane & 15;
            const uint32_t dst = sb + SM_HS + ((lane >> 4) * 16 + (f & 3) * 4 + (f >> 2)) * 4;
            unsigned w[7], n = 0;
            while (true) {
                unsigned bad = 0;
#pragma unroll
                for (int i = 0; i < 7; i++) w[i] = ld_rlx(hp + i * 32);
#pragma unroll
                for (int i = 0; i < 7; i++) bad |= tag_bad(w[i], tag);
                if (!__any_sync(~0u, bad)) break;
                spin_check(n);
                __nanosleep(200);
            }
#pragma unroll
            for (int i = 0; i < 7; i++) sts32(dst + i * 128, bf_bits(untag(w[i])));
            __syncwarp();
            if (lane == 0) mbar_arrive(bar_hs);
        }
        TL(9);
        {
            mbar_wait(bar_ml, 0);
            const uint2 ml = lds64(sb + SM_ML + (lane & 7) * 8);
            float M = as_f(ml.x);
#pragma unroll
            for (int o = 4; o > 0; o >>= 1) M = fmaxf(M, __shfl_xor_sync(~0u, M, o));
            M = untag(__float_as_uint(M));
            float L = as_f(ml.y) * ex2((as_f(ml.x) - M) * SM_SCALE);
#pragma unroll
            for (int o = 4; o > 0; o >>= 1) L += __shfl_xor_sync(~0u, L, o);
            unsigned* sp = scr + G_ST + (h * 2 + b) * 32;
            if (lane < 8) st_rlx(sp + s * 8 + lane, tagw((lane & 1) ? L : M, tag));
            uint2 w; unsigned n = 0;
            while (true) {
                w = ld_rlx2(sp + (lane & 3) * 8);
                if (!__any_sync(~0u, tag_bad(w.x, tag) | tag_bad(w.y, tag))) break;
                spin_check(n);
                __nanosleep(200);
            }
            const float ms = untag(w.x);
            float M2 = fmaxf(ms, __shfl_xor_sync(~0u, ms, 1));
            M2 = fmaxf(M2, __shfl_xor_sync(~0u, M2, 2));
            float L2 = untag(w.y) * ex2((ms - M2) * SM_SCALE);
            L2 += __shfl_xor_sync(~0u, L2, 1);
            L2 += __shfl_xor_sync(~0u, L2, 2);
            if (lane < NW) sts32(sb + SM_FAC + lane * 4, __float_as_uint((b ? g1 : g0) * ex2((as_f(ml.x) - M2) * SM_SCALE) * rcp(L2)));
            __syncwarp();
            if (lane == 0) mbar_arrive(bar_fac);
        }
        TL(10);
        if (c < 112) {
            const unsigned* op = scr + G_O2 + c * NH * 8 + 4 * lane;
            uint4 w; unsigned n = 0;
            while (true) {
                w = ld_rlx4(op);
                if (!__any_sync(~0u, tag_bad(w.x, tag) | tag_bad(w.y, tag) | tag_bad(w.z, tag) | tag_bad(w.w, tag))) break;
                spin_check(n);
            }
            TL(14);
            MC(f0);
            float a0 = untag(w.x), a1 = untag(w.y), a2 = untag(w.z), a3 = untag(w.w);
#pragma unroll
            for (int o = 16; o > 1; o >>= 1) {
                a0 += __shfl_xor_sync(~0u, a0, o); a1 += __shfl_xor_sync(~0u, a1, o);
                a2 += __shfl_xor_sync(~0u, a2, o); a3 += __shfl_xor_sync(~0u, a3, o);
            }
            TL(12);
            MC(f1);
            if (lane < 2) {
                uint2 o2;
                o2.x = bf_bits(a0) | (bf_bits(a1) << 16);
                o2.y = bf_bits(a2) | (bf_bits(a3) << 16);
                *reinterpret_cast<uint2*>(out + (c / 56) * DM + 8 * (c % 56) + 4 * lane) = o2;
            }
            TL(13);
            if (c == 0 && lane == 0) st_rlx(scr + G_STATE, tag);
        }
        TL(11);
        TDUMP_A();
    }
}

}

extern "C" void kernel_launch(void* const* d_in, const int* in_sizes, int n_in, void* d_out, int out_size) {
    (void)in_sizes; (void)n_in; (void)out_size;
    static bool configured = false;
    if (!configured) {
        cudaFuncSetAttribute(fused_decode_kernel, cudaFuncAttributeMaxDynamicSharedMemorySize, SM_TOTAL);
        configured = true;
    }
    const __nv_bfloat16* x  = (const __nv_bfloat16*)d_in[0];
    const __nv_bfloat16* Kc = (const __nv_bfloat16*)d_in[1];
    const __nv_bfloat16* Vc = (const __nv_bfloat16*)d_in[2];
    const __nv_bfloat16* wq = (const __nv_bfloat16*)d_in[3];
    const __nv_bfloat16* wo = (const __nv_bfloat16*)d_in[4];
    const __nv_bfloat16* Wg = (const __nv_bfloat16*)d_in[6];
    const __nv_bfloat16* Wu = (const __nv_bfloat16*)d_in[7];
    const __nv_bfloat16* Wd = (const __nv_bfloat16*)d_in[8];
    const __nv_bfloat16* gw = (const __nv_bfloat16*)d_in[9];
    fused_decode_kernel<<<NCTA, NTHREADS, SM_TOTAL, cudaStreamPerThread>>>(x, Kc, Vc, wq, wo, Wg, Wu, Wd, gw, (__nv_bfloat16*)d_out);
}
```

```cpp
#include <cuda.h>
#include <cuda_runtime.h>
#include <cuda_bf16.h>
#include <stdint.h>

namespace {

constexpr int DM    = 448;
constexpr int NH    = 16;
constexpr int SK    = 4096;
constexpr int DH    = 256;
constexpr int DFF   = 1792;
constexpr int NCTA  = 128;
constexpr int NW    = 8;
constexpr int SLOTS = 4;
constexpr int DEPTH = 2;
constexpr int FEED  = 14;
constexpr int PACE_T0 = 180, PACE_STAG = 160, PACE_TAU = 1295, PACE_DEL = 130, PACE_J = 10;
constexpr int TILE_BYTES = 8 * DH * 2;
constexpr int NT    = 16;
constexpr int NTHREADS = (NW + 1) * 32;
constexpr float LOG2E = 1.4426950408889634f;
constexpr float SM_SCALE = 0.0625f * LOG2E;
constexpr unsigned SPIN_LIMIT = 1u << 22;

constexpr int SM_FIFO  = 0;
constexpr int SM_STAGE = SM_FIFO + NW * SLOTS * TILE_BYTES;
constexpr int SM_WD    = SM_STAGE + 2 * DM * 32;
constexpr int SM_PW    = SM_WD + 112 * 128;
constexpr int SM_QRED  = SM_PW + NW * 144 * 4;
constexpr int SM_QS    = SM_QRED + NW * 128 * 4;
constexpr int SM_XS    = SM_QS + 512;
constexpr int SM_HS    = SM_XS + 3 * DM * 2;
constexpr int SM_ML    = SM_HS + 7 * 32 * 4;
constexpr int SM_FAC   = SM_ML + NW * 8;
constexpr int SM_TAG   = SM_FAC + NW * 4;
constexpr int SM_BAR   = SM_TAG + 8;
constexpr int SM_TOTAL = SM_BAR + (NW * SLOTS + 6) * 8;
static_assert(SM_BAR % 8 == 0 && SM_WD % 1024 == 0 && SM_XS % 16 == 0, "align");
static_assert(SM_TOTAL <= 232448, "smem");
static_assert(DEPTH < SLOTS && FEED < NW * SLOTS && SLOTS == 4 && NT == 16, "FIFO");

constexpr int G_QP = 0;
constexpr int G_O1 = G_QP + NCTA * 128;
constexpr int G_O2 = G_O1 + NCTA * 256;
constexpr int G_HH = G_O2 + 112 * NH * 8;
constexpr int G_ST = G_HH + NCTA * 32;
constexpr int G_STATE = G_ST + NCTA * 8;
__device__ __align__(128) unsigned g_scr[G_STATE + 32];

__device__ __forceinline__ void mbar_init(uint32_t bar, uint32_t cnt) {
    asm volatile("mbarrier.init.shared::cta.b64 [%0], %1;" :: "r"(bar), "r"(cnt) : "memory");
}
__device__ __forceinline__ void mbar_expect_tx(uint32_t bar, uint32_t bytes) {
    asm volatile("mbarrier.arrive.expect_tx.shared::cta.b64 _, [%0], %1;" :: "r"(bar), "r"(bytes) : "memory");
}
__device__ __forceinline__ void mbar_arrive(uint32_t bar) {
    asm volatile("mbarrier.arrive.shared::cta.b64 _, [%0];" :: "r"(bar) : "memory");
}
__device__ __forceinline__ bool mbar_test(uint32_t bar, uint32_t parity) {
    uint32_t ok;
    asm volatile("{\n.reg .pred p;\nmbarrier.test_wait.parity.shared::cta.b64 p, [%1], %2;\nselp.u32 %0, 1, 0, p;\n}"
                 : "=r"(ok) : "r"(bar), "r"(parity) : "memory");
    return ok;
}
__device__ __forceinline__ void mbar_wait(uint32_t bar, uint32_t parity) {
    asm volatile("{\n.reg .pred p, q;\n.reg .u32 n;\nmov.u32 n, 0;\n"
                 "WAIT_LOOP:\nmbarrier.try_wait.parity.shared::cta.b64 p, [%0], %1;\n@p bra WAIT_DONE;\n"
                 "add.u32 n, n, 1;\nsetp.lt.u32 q, n, %2;\n@q bra WAIT_LOOP;\ntrap;\nWAIT_DONE:\n}"
                 :: "r"(bar), "r"(parity), "n"(SPIN_LIMIT) : "memory");
}
__device__ __forceinline__ void bulk_g2s(uint32_t dst, const void* src, uint32_t bar, uint64_t pol) {
    asm volatile("cp.async.bulk.shared::cluster.global.mbarrier::complete_tx::bytes.L2::cache_hint [%0], [%1], %2, [%3], %4;"
                 :: "r"(dst), "l"(src), "n"(TILE_BYTES), "r"(bar), "l"(pol) : "memory");
}
__device__ __forceinline__ void bulk_g2s_plain(uint32_t dst, const void* src, uint32_t bytes, uint32_t bar) {
    asm volatile("cp.async.bulk.shared::cluster.global.mbarrier::complete_tx::bytes [%0], [%1], %2, [%3];"
                 :: "r"(dst), "l"(src), "r"(bytes), "r"(bar) : "memory");
}
__device__ __forceinline__ void tma_2d(uint32_t dst, const CUtensorMap* map, int col, int row, uint32_t bar) {
    asm volatile("cp.async.bulk.tensor.2d.shared::cluster.global.mbarrier::complete_tx::bytes [%0], [%1, {%2, %3}], [%4];"
                 :: "r"(dst), "l"(map), "r"(col), "r"(row), "r"(bar) : "memory");
}
__device__ __forceinline__ uint64_t stream_policy() {
    uint64_t pol;
    asm volatile("createpolicy.fractional.L2::evict_first.b64 %0, 1.0;" : "=l"(pol));
    return pol;
}
__device__ __forceinline__ uint4 ldg128(const void* p) {
    uint4 v;
    asm volatile("ld.global.nc.L1::no_allocate.v4.u32 {%0,%1,%2,%3}, [%4];" : "=r"(v.x), "=r"(v.y), "=r"(v.z), "=r"(v.w) : "l"(p));
    return v;
}
__device__ __forceinline__ unsigned ldg_u16(const __nv_bfloat16* p) {
    unsigned short v; asm volatile("ld.global.nc.u16 %0, [%1];" : "=h"(v) : "l"(p)); return v;
}
__device__ __forceinline__ uint4 lds128(uint32_t a) {
    uint4 v;
    asm volatile("ld.shared.v4.u32 {%0,%1,%2,%3}, [%4];" : "=r"(v.x), "=r"(v.y), "=r"(v.z), "=r"(v.w) : "r"(a) : "memory");
    return v;
}
__device__ __forceinline__ uint2 lds64(uint32_t a) {
    uint2 v; asm volatile("ld.shared.v2.u32 {%0,%1}, [%2];" : "=r"(v.x), "=r"(v.y) : "r"(a) : "memory"); return v;
}
__device__ __forceinline__ unsigned lds32(uint32_t a) {
    unsigned v; asm volatile("ld.shared.u32 %0, [%1];" : "=r"(v) : "r"(a) : "memory"); return v;
}
__device__ __forceinline__ unsigned lds16(uint32_t a) {
    unsigned short v; asm volatile("ld.shared.u16 %0, [%1];" : "=h"(v) : "r"(a) : "memory"); return v;
}
__device__ __forceinline__ void sts128f(uint32_t a, float x, float y, float z, float w) {
    asm volatile("st.shared.v4.f32 [%0], {%1,%2,%3,%4};" :: "r"(a), "f"(x), "f"(y), "f"(z), "f"(w) : "memory");
}
__device__ __forceinline__ void sts64f(uint32_t a, float x, float y) {
    asm volatile("st.shared.v2.f32 [%0], {%1,%2};" :: "r"(a), "f"(x), "f"(y) : "memory");
}
__device__ __forceinline__ void sts32(uint32_t a, unsigned v) { asm volatile("st.shared.u32 [%0], %1;" :: "r"(a), "r"(v) : "memory"); }
__device__ __forceinline__ void sts16(uint32_t a, unsigned v) { asm volatile("st.shared.u16 [%0], %1;" :: "r"(a), "h"((unsigned short)v) : "memory"); }
__device__ __forceinline__ unsigned ld_rlx(const unsigned* p) {
    unsigned v; asm volatile("ld.relaxed.gpu.global.u32 %0, [%1];" : "=r"(v) : "l"(p) : "memory"); return v;
}
__device__ __forceinline__ uint2 ld_rlx2(const unsigned* p) {
    uint2 v; asm volatile("ld.relaxed.gpu.global.v2.u32 {%0,%1}, [%2];" : "=r"(v.x), "=r"(v.y) : "l"(p) : "memory"); return v;
}
__device__ __forceinline__ void st_rlx(unsigned* p, unsigned v) {
    asm volatile("st.relaxed.gpu.global.u32 [%0], %1;" :: "l"(p), "r"(v) : "memory");
}
__device__ __forceinline__ void st_rlx4(unsigned* p, unsigned a, unsigned b, unsigned c, unsigned d) {
    asm volatile("st.relaxed.gpu.global.v4.u32 [%0], {%1,%2,%3,%4};" :: "l"(p), "r"(a), "r"(b), "r"(c), "r"(d) : "memory");
}
__device__ __forceinline__ unsigned tagw(float v, unsigned tag) { return (__float_as_uint(v) & ~3u) | tag; }
__device__ __forceinline__ float untag(unsigned w) { return __uint_as_float(w & ~3u); }
__device__ __forceinline__ unsigned tag_bad(unsigned w, unsigned tag) { return (w ^ tag) & 3u; }
__device__ __forceinline__ void spin_check(unsigned& n) { if (++n > SPIN_LIMIT) __trap(); }
__device__ __forceinline__ unsigned bf_bits(float v) { return (unsigned)__bfloat16_as_ushort(__float2bfloat16_rn(v)); }
__device__ __forceinline__ float as_f(unsigned v) { return __uint_as_float(v); }
__device__ __forceinline__ float bf_round(float v) { return as_f(bf_bits(v) << 16); }
__device__ __forceinline__ float ex2(float v) { float r; asm("ex2.approx.ftz.f32 %0, %1;" : "=f"(r) : "f"(v)); return r; }
__device__ __forceinline__ float rcp(float v) { float r; asm("rcp.approx.ftz.f32 %0, %1;" : "=f"(r) : "f"(v)); return r; }
__device__ __forceinline__ void mma16816(float (&c)[4], unsigned a0, unsigned a1, unsigned a2, unsigned a3, unsigned b0, unsigned b1) {
    asm volatile("mma.sync.aligned.m16n8k16.row.col.f32.bf16.bf16.f32 {%0,%1,%2,%3}, {%4,%5,%6,%7}, {%8,%9}, {%0,%1,%2,%3};"
                 : "+f"(c[0]), "+f"(c[1]), "+f"(c[2]), "+f"(c[3]) : "r"(a0), "r"(a1), "r"(a2), "r"(a3), "r"(b0), "r"(b1));
}
__device__ __forceinline__ void mma16816(float (&c)[4], const uint4& a, unsigned b0, unsigned b1) { mma16816(c, a.x, a.y, a.z, a.w, b0, b1); }
__device__ __forceinline__ unsigned gtime() { unsigned v; asm volatile("mov.u32 %0, %%globaltimer_lo;" : "=r"(v)); return v; }
__device__ __forceinline__ bool elect_one() {
    uint32_t p;
    asm volatile("{\n.reg .pred p;\nelect.sync _|p, 0xffffffff;\nselp.u32 %0, 1, 0, p;\n}" : "=r"(p));
    return p;
}
__device__ __forceinline__ void bar_sync(int id, int n)   { asm volatile("bar.sync %0, %1;" :: "r"(id), "r"(n) : "memory"); }
__device__ __forceinline__ void bar_arrive(int id, int n) { asm volatile("bar.arrive %0, %1;" :: "r"(id), "r"(n) : "memory"); }


__global__ void __launch_bounds__(NTHREADS, 1)
fused_decode_kernel(const __nv_bfloat16* __restrict__ x, const __nv_bfloat16* __restrict__ Kc, const __nv_bfloat16* __restrict__ Vc,
                    const __nv_bfloat16* __restrict__ wq, const __nv_bfloat16* __restrict__ gate_w, __nv_bfloat16* __restrict__ out,
                    const __grid_constant__ CUtensorMap tm_wg, const __grid_constant__ CUtensorMap tm_wu,
                    const __grid_constant__ CUtensorMap tm_wd, const __grid_constant__ CUtensorMap tm_wo,
                    int pace_t0, int pace_stag, int pace_tau, int pace_del)
{
    extern __shared__ __align__(128) unsigned char smem[];
    uint32_t sb;
    asm volatile("mov.u32 %0, %1;" : "=r"(sb) : "r"((uint32_t)__cvta_generic_to_shared(smem)));
    unsigned* scr;
    asm volatile("mov.u64 %0, %1;" : "=l"(scr) : "l"(g_scr));
    const int c = blockIdx.x, h = c >> 3, r = c & 7, b = r >> 2, s = r & 3;
    const int warp = __shfl_sync(~0u, (int)(threadIdx.x >> 5), 0), lane = threadIdx.x & 31, g = lane >> 2, t = lane & 3;
    const uint32_t bar_ml  = sb + SM_BAR + NW * SLOTS * 8;
    const uint32_t bar_hs  = bar_ml + 8;
    const uint32_t bar_fac = bar_ml + 16;
    const uint32_t bar_q   = bar_ml + 24;
    const uint32_t bar_w   = bar_ml + 32;
    const uint32_t bar_f   = bar_ml + 40;
    const int bb = (g >> 1) & 1;
    const unsigned mulp = (g & 1) ? 65536u : 1u;
    const unsigned mul0 = (g & 4) ? 0u : mulp, mul1 = (g & 4) ? mulp : 0u;

    if (warp < NW) {
        const unsigned t_line = gtime() + (unsigned)(pace_t0 + r * pace_stag);
        auto pace = [&](int j) {
            const unsigned due = t_line + j * pace_tau + (j < PACE_J ? j : PACE_J) * pace_del;
#pragma unroll 1
            for (unsigned n = 0; (int)(gtime() - due) < 0 && n < SPIN_LIMIT; n++) {}
        };
        unsigned xb[7];
        uint4 wv[7];
        {
            const int row = 224 * (r & 1) + 28 * warp + t;
            const __nv_bfloat16* xp = x + bb * DM + row;
            const __nv_bfloat16* wp = wq + (size_t)row * (NH * DH) + 256 * h + 64 * (r >> 1) + 8 * g;
#pragma unroll
            for (int j = 0; j < 7; j++) wv[j] = ldg128(wp + (size_t)(4 * j) * (NH * DH));
#pragma unroll
            for (int j = 0; j < 7; j++) xb[j] = ldg_u16(xp + 4 * j);
        }
        unsigned state = 0;
        if (warp == 0) state = ld_rlx(scr + G_STATE);
        const uint32_t fifo = sb + SM_FIFO + warp * SLOTS * TILE_BYTES;
        const uint32_t fbar = sb + SM_BAR + warp * SLOTS * 8;
        if (lane == 0) {
#pragma unroll
            for (int i = 0; i < SLOTS; i++) mbar_init(fbar + i * 8, 1);
            asm volatile("fence.mbarrier_init.release.cluster;" ::: "memory");
        }
        __syncwarp();
        bar_arrive(3, NTHREADS);
        const size_t kv_off = ((size_t)(b * NH + h) * SK + s * 1024 + warp * 8) * DH;
        const unsigned char* const vbase = reinterpret_cast<const unsigned char*>(Vc + kv_off);
        const unsigned char* nsrc = reinterpret_cast<const unsigned char*>(Kc + kv_off) + SLOTS * NW * TILE_BYTES;
        const uint64_t pol = stream_policy();
        auto issue = [&](int slot) {
            mbar_expect_tx(fbar + slot * 8, TILE_BYTES);
            bulk_g2s(fifo + slot * TILE_BYTES, nsrc, fbar + slot * 8, pol);
        };
        unsigned* const qp_out = scr + G_QP + c * 128 + threadIdx.x;
        unsigned* const o1_out = scr + G_O1 + c * 256 + threadIdx.x;
        unsigned* const o2_out = scr + G_O2 + ((((threadIdx.x >> 2) & 1) * 56 + 8 * r + (threadIdx.x >> 4)) * NH + h) * 8 + 4 * ((threadIdx.x >> 3) & 1) + (threadIdx.x & 3);
        if (warp < 4) st_rlx(qp_out, 0u);
        st_rlx(o1_out, 0u);
        if (warp < 4 && r < 7) st_rlx(o2_out, 0u);

        {
            float c0[4] = {0.f, 0.f, 0.f, 0.f}, c1[4] = {0.f, 0.f, 0.f, 0.f};
#pragma unroll
            for (int j = 0; j < 7; j++) mma16816((j & 1) ? c1 : c0, wv[j], xb[j] * mul0, xb[j] * mul1);
            sts128f(sb + SM_QRED + (warp * 128 + (t & 1) * 64 + 8 * g + 4 * (t >> 1)) * 4, c0[0] + c1[0], c0[1] + c1[1], c0[2] + c1[2], c0[3] + c1[3]);
        }
        if (threadIdx.x == 0) sts32(sb + SM_TAG, state == 3u ? 1u : state + 1u);
        bar_sync(4, NW * 32);
        const unsigned tag = lds32(sb + SM_TAG);
        if (warp < 4) {
            const uint32_t qr = sb + SM_QRED + threadIdx.x * 4;
            float v = 0.f;
#pragma unroll
            for (int w = 0; w < NW; w++) v += as_f(lds32(qr + w * 512));
            st_rlx(qp_out, tagw(v, tag));
        }
        {
            const unsigned* qp = scr + G_QP + (h * 8 + (warp & 6)) * 128 + b * 64 + (warp & 1) * 32 + lane;
            unsigned w0, w1, n = 0;
            do { w0 = ld_rlx(qp); w1 = ld_rlx(qp + 128); spin_check(n); } while (__any_sync(~0u, tag_bad(w0, tag) | tag_bad(w1, tag)));
            const int k = (lane >> 1) & 3;
            sts16(sb + SM_QS + (4 * warp + (lane >> 3)) * 16 + ((k & 1) * 2 + (k >> 1)) * 4 + (lane & 1) * 2, bf_bits(untag(w0) + untag(w1)));
        }
        bar_sync(1, NTHREADS);
        if (threadIdx.x == 0) mbar_arrive(bar_q);
        uint2 qf[8];
#pragma unroll
        for (int j = 0; j < 8; j++) qf[j] = lds64(sb + SM_QS + (t + 4 * (j ^ (g & 1))) * 16 + bb * 8);

        float s0 = 0.f, s1 = 0.f, s2 = 0.f, s3 = 0.f;
        int slot = 0; uint32_t phase = 0;
#pragma unroll 1
        for (int it = 0; it < NT; it++) {
            mbar_wait(fbar + slot * 8, phase);
            if (it + DEPTH >= SLOTS) {
                if (it + DEPTH == NT) nsrc = vbase;
                pace(it + DEPTH);
                if (elect_one()) issue((slot + DEPTH) % SLOTS);
                nsrc += NW * TILE_BYTES;
                asm volatile("" : "+l"(nsrc));
            }
            const uint32_t tile = fifo + slot * TILE_BYTES + g * 512 + t * 16;
            float c0[4] = {0.f, 0.f, 0.f, 0.f}, c1[4] = {0.f, 0.f, 0.f, 0.f};
#pragma unroll
            for (int j = 0; j < 8; j += 2) {
                const uint4 X0 = lds128(tile + 64 * j + 64 * (g & 1)), X1 = lds128(tile + 64 * (j + 1) - 64 * (g & 1));
                mma16816(c0, X0, qf[j].x, qf[j].y);
                mma16816(c1, X1, qf[j + 1].x, qf[j + 1].y);
            }
            __syncwarp();
            const float v = (t & 1) ? ((g & 1) ? c0[3] + c1[3] : c0[2] + c1[2]) : ((g & 1) ? c0[1] + c1[1] : c0[0] + c1[0]);
            const float sc = bf_round(v + __shfl_xor_sync(~0u, v, 1));
            if ((it & 3) == t) {
                if (it < 4) s0 = sc; else if (it < 8) s1 = sc; else if (it < 12) s2 = sc; else s3 = sc;
            }
            if (++slot == SLOTS) { slot = 0; phase ^= 1; }
        }
        const uint32_t pw = sb + SM_PW + warp * 144 * 4;
        {
            float m = fmaxf(fmaxf(s0, s1), fmaxf(s2, s3));
#pragma unroll
            for (int o = 16; o > 0; o >>= 1) m = fmaxf(m, __shfl_xor_sync(~0u, m, o));
            const float p0 = ex2((s0 - m) * SM_SCALE), p1 = ex2((s1 - m) * SM_SCALE);
            const float p2 = ex2((s2 - m) * SM_SCALE), p3 = ex2((s3 - m) * SM_SCALE);
            float l = (p0 + p1) + (p2 + p3);
#pragma unroll
            for (int o = 16; o > 0; o >>= 1) l += __shfl_xor_sync(~0u, l, o);
            const uint32_t pp = pw + ((g & 3) * 36 + 2 * t + (g >> 2)) * 4;
            sts32(pp, bf_bits(p0)); sts32(pp + 32, bf_bits(p1)); sts32(pp + 64, bf_bits(p2)); sts32(pp + 96, bf_bits(p3));
            if (lane == 0) {
                sts64f(sb + SM_ML + warp * 8, m, l);
                mbar_arrive(bar_ml);
            }
            __syncwarp();
        }
        float acc[4][2][4];
#pragma unroll
        for (int i = 0; i < 4; i++)
#pragma unroll
            for (int j = 0; j < 2; j++)
#pragma unroll
                for (int k = 0; k < 4; k++) acc[i][j][k] = 0.f;
        const unsigned mulv = ((g >> 1) == t) ? mulp : 0u;
        float C0[4] = {0.f, 0.f, 0.f, 0.f}, C1[4] = {0.f, 0.f, 0.f, 0.f}, fac = 0.f;
        const uint32_t fo0 = (2 * t) * 128 + ((g ^ (2 * t)) << 4), fo1 = (2 * t + 1) * 128 + ((g ^ (2 * t + 1)) << 4);
#pragma unroll 1
        for (int iv = 0; iv < NT; iv++) {
            mbar_wait(fbar + slot * 8, phase);
            if (iv + DEPTH < NT) { pace(NT + iv + DEPTH); if (elect_one()) issue((slot + DEPTH) % SLOTS); }
            if (iv == NT - 1 && r < 7 && elect_one()) {
                mbar_expect_tx(fbar + 8, TILE_BYTES);
                tma_2d(fifo + TILE_BYTES, &tm_wo, 64 * r, 256 * h + 32 * warp, fbar + 8);
            }
            nsrc += NW * TILE_BYTES;
            asm volatile("" : "+l"(nsrc));
            const uint2 P = lds64(pw + (t * 36 + 2 * iv) * 4);
            const unsigned B0 = P.x * mulv, B1 = P.y * mulv;
            const uint32_t tile = fifo + slot * TILE_BYTES + t * 512 + (8 * (g >> 1) + (g & 1)) * 16;
#pragma unroll
            for (int rr = 0; rr < 4; rr++) {
                const uint32_t a = tile + 32 * (t ^ rr);
                const uint4 X = lds128(a), Y = lds128(a + 4 * 512);
                mma16816(acc[rr][0], X, B0, 0u);
                mma16816(acc[rr][1], X, 0u, B0);
                mma16816(acc[rr][0], Y, B1, 0u);
                mma16816(acc[rr][1], Y, 0u, B1);
            }
            __syncwarp();
            if (iv == NT - 2) {
                mbar_wait(bar_fac, 0);
                fac = as_f(lds32(sb + SM_FAC + warp * 4));
            }
            if (iv == NT - 2 && r < 7) {
                mbar_wait(bar_w, 0);
                mbar_wait(bar_hs, 0);
                if (warp < 7) {
                    const uint4 Hs = lds128(sb + SM_HS + (warp * 32 + bb * 16 + t * 4) * 4);
                    const uint32_t wd = sb + SM_WD + warp * 2048;
                    mma16816(C0, lds128(wd + fo0), Hs.x * mul0, Hs.x * mul1);
                    mma16816(C1, lds128(wd + fo1), Hs.y * mul0, Hs.y * mul1);
                    mma16816(C0, lds128(wd + 1024 + fo0), Hs.z * mul0, Hs.z * mul1);
                    mma16816(C1, lds128(wd + 1024 + fo1), Hs.w * mul0, Hs.w * mul1);
                }
            }
            if (++slot == SLOTS) { slot = 0; phase ^= 1; }
        }
        {
            float f[8];
#pragma unroll
            for (int j = 0; j < 2; j++)
#pragma unroll
                for (int k = 0; k < 4; k++)
                    f[4 * j + k] = ((acc[0][j][k] + __shfl_xor_sync(~0u, acc[1][j][k], 1)) +
                                    (__shfl_xor_sync(~0u, acc[2][j][k], 2) + __shfl_xor_sync(~0u, acc[3][j][k], 3))) * fac;
            const uint32_t dst = fifo + (8 * (g >> 1) + 2 * t + (g & 1)) * 32;
            sts128f(dst, f[0], f[1], f[2], f[3]);
            sts128f(dst + 16, f[4], f[5], f[6], f[7]);
        }
        bar_sync(2, NW * 32);
        {
            const uint32_t a = sb + SM_FIFO + threadIdx.x * 4;
            float v[8];
#pragma unroll
            for (int w = 0; w < NW; w++) v[w] = as_f(lds32(a + w * SLOTS * TILE_BYTES));
            st_rlx(o1_out, tagw(((v[0] + v[1]) + (v[2] + v[3])) + ((v[4] + v[5]) + (v[6] + v[7])), tag));
        }
        if (r == 7) return;
        unsigned sel0, sel1;
        {
            const unsigned sel = (g & 1) ? (0x44u | (2 * bb) << 8 | (2 * bb + 1) << 12) : ((2 * bb) | (2 * bb + 1) << 4 | 0x4400u);
            sel0 = (g & 4) ? 0x4444u : sel; sel1 = (g & 4) ? sel : 0x4444u;
            asm volatile("" : "+r"(sel0), "+r"(sel1));
        }
        unsigned pk;
        {
            const unsigned* op = scr + G_O1 + h * 8 * 256 + threadIdx.x;
            unsigned w[8], pending = 0xffu, n = 0;
            while (true) {
#pragma unroll
                for (int i = 0; i < 8; i++) if (pending >> i & 1) w[i] = ld_rlx(op + i * 256);
                unsigned bad = 0;
#pragma unroll
                for (int i = 0; i < 8; i++) bad |= (tag_bad(w[i], tag) ? 1u : 0u) << i;
                pending = __reduce_or_sync(~0u, bad);
                if (!pending) break;
                spin_check(n);
            }
            pk = bf_bits((untag(w[0]) + untag(w[1])) + (untag(w[2]) + untag(w[3])))
               | bf_bits((untag(w[4]) + untag(w[5])) + (untag(w[6]) + untag(w[7]))) << 16;
        }
        {
            float C2[4] = {0.f, 0.f, 0.f, 0.f}, C3[4] = {0.f, 0.f, 0.f, 0.f};
            unsigned Bf[16];
#pragma unroll
            for (int j = 0; j < 8; j++) {
                const unsigned o = __shfl_sync(~0u, pk, 8 * (j >> 1) + 2 * t + (j & 1));
                Bf[2 * j] = __byte_perm(o, 0u, sel0); Bf[2 * j + 1] = __byte_perm(o, 0u, sel1);
            }
            mbar_wait(fbar + 8, 0);
#pragma unroll
            for (int j = 0; j < 8; j++)
                mma16816((j & 2) ? ((j & 1) ? C3 : C2) : ((j & 1) ? C1 : C0),
                         lds128(fifo + TILE_BYTES + (j >> 1) * 1024 + ((j & 1) ? fo1 : fo0)), Bf[2 * j], Bf[2 * j + 1]);
            sts128f(fifo + 2048 + lane * 16, (C0[0] + C1[0]) + (C2[0] + C3[0]), (C0[1] + C1[1]) + (C2[1] + C3[1]),
                    (C0[2] + C1[2]) + (C2[2] + C3[2]), (C0[3] + C1[3]) + (C2[3] + C3[3]));
        }
        bar_sync(2, NW * 32);
        if (warp < 4) {
            const uint32_t a = sb + SM_FIFO + 2048 + threadIdx.x * 4;
            float v[8];
#pragma unroll
            for (int w = 0; w < NW; w++) v[w] = as_f(lds32(a + w * SLOTS * TILE_BYTES));
            st_rlx(o2_out, tagw(((v[0] + v[1]) + (v[2] + v[3])) + ((v[4] + v[5]) + (v[6] + v[7])), tag));
        }
    } else {
        if (lane == 0) {
            mbar_init(bar_ml, NW); mbar_init(bar_hs, 32); mbar_init(bar_fac, NW); mbar_init(bar_q, 1); mbar_init(bar_w, 1); mbar_init(bar_f, 1);
            asm volatile("fence.mbarrier_init.release.cluster;" ::: "memory");
        }
        __syncwarp();
        bar_arrive(1, NTHREADS);
        {
            bar_sync(3, NTHREADS);
            if (elect_one()) {
                const unsigned char* src = reinterpret_cast<const unsigned char*>(Kc + ((size_t)(b * NH + h) * SK + s * 1024) * DH);
                const uint64_t pol = stream_policy();
                bool open = false;
#pragma unroll 1
                for (int k = 0; k < NW * SLOTS; k++) {
                    if (k >= FEED && !open) {
                        const int kp = k - FEED;
                        const uint32_t pb = sb + SM_BAR + ((kp & (NW - 1)) * SLOTS + (kp >> 3)) * 8;
                        unsigned n = 0;
                        while (!mbar_test(pb, 0)) { if (mbar_test(bar_q, 0)) { open = true; break; } spin_check(n); }
                    }
                    const int fi = (k & (NW - 1)) * SLOTS + (k >> 3);
                    mbar_expect_tx(sb + SM_BAR + fi * 8, TILE_BYTES);
                    bulk_g2s(sb + SM_FIFO + fi * TILE_BYTES, src, sb + SM_BAR + fi * 8, pol);
                    src += TILE_BYTES;
                }
            }
            __syncwarp();
        }
        mbar_wait(bar_q, 0);
        const unsigned tag = lds32(sb + SM_TAG);
        const int set = g >> 2;
        if (elect_one()) {
            const bool ffn = r > 0;
            mbar_expect_tx(bar_f, 3 * DM * 2 + (ffn ? 2 * DM * 32 : 0));
            bulk_g2s_plain(sb + SM_XS, x, 2 * DM * 2, bar_f);
            bulk_g2s_plain(sb + SM_XS + 2 * DM * 2, gate_w, DM * 2, bar_f);
            if (ffn) {
                const int col = 112 * h + 16 * (r - 1);
                tma_2d(sb + SM_STAGE, &tm_wg, col, 0, bar_f);
                tma_2d(sb + SM_STAGE + 224 * 32, &tm_wg, col, 224, bar_f);
                tma_2d(sb + SM_STAGE + DM * 32, &tm_wu, col, 0, bar_f);
                tma_2d(sb + SM_STAGE + DM * 32 + 224 * 32, &tm_wu, col, 224, bar_f);
            }
        }
        mbar_wait(bar_f, 0);
        float g0, g1;
        {
            float c1[4] = {0.f, 0.f, 0.f, 0.f}, c2[4] = {0.f, 0.f, 0.f, 0.f}, cz[4] = {0.f, 0.f, 0.f, 0.f};
            uint32_t wa = sb + SM_STAGE + ((g >> 1) & 1) * (DM * 32) + (8 * set + t) * 32 + (g & 1) * 16;
            uint32_t xa = sb + SM_XS + (bb * DM + 8 * set + t) * 2;
            uint32_t za = sb + SM_XS + ((g & 1) * DM + 2 * t) * 2;
            uint32_t zb = sb + SM_XS + (2 * DM + 2 * t) * 2;
#pragma unroll 1
            for (int j = 0; j < 28; j++) {
                const uint2 X0 = lds64(wa), Y0 = lds64(wa + 128), X1 = lds64(wa + 8), Y1 = lds64(wa + 136);
                const unsigned B0 = lds16(xa) * mulp, B1 = lds16(xa + 8) * mulp;
                const unsigned a0 = lds32(za), a1 = lds32(za + 16);
                mma16816(c1, X0.x, X0.y, Y0.x, Y0.y, B0, B1);
                mma16816(c2, X1.x, X1.y, Y1.x, Y1.y, B0, B1);
                mma16816(cz, a0, a0, a1, a1, lds32(zb), lds32(zb + 16));
                wa += 512; xa += 32; za += 32; zb += 32;
            }
            const float gz = bf_round(rcp(1.f + ex2(-LOG2E * bf_round(cz[0]))));
            g0 = __shfl_sync(~0u, gz, 0);
            g1 = __shfl_sync(~0u, gz, 4);
            const float sc = bf_round(1.f - ((t & 1) ? g1 : g0));
            unsigned hw[4];
#pragma unroll
            for (int k = 0; k < 4; k++) {
                const float v = (set ? c2[k] : c1[k]) + __shfl_xor_sync(~0u, set ? c1[k] : c2[k], 18);
                const float u = __shfl_xor_sync(~0u, v, 8);
                hw[k] = tagw((v > 0.f ? v * u : 0.f) * sc, tag);
            }
            if (r > 0 && (t >> 1) == set && !(g & 2))
                st_rlx4(scr + G_HH + (c - 1) * 32 + (t & 1) * 16 + 8 * (g & 1) + 4 * set, hw[0], hw[1], hw[2], hw[3]);
        }
        if (r < 7) {
            if (elect_one()) {
                mbar_expect_tx(bar_w, 112 * 128);
                tma_2d(sb + SM_WD, &tm_wd, 64 * r, 112 * h, bar_w);
            }
            const unsigned* hp = scr + G_HH + h * 8 * 32 + lane;
            const int f = lane & 15;
            const uint32_t hd = sb + SM_HS + ((lane >> 4) * 16 + ((f >> 1) & 3) * 4 + (f >> 3) * 2 + (f & 1)) * 4;
            unsigned w[7], n = 0;
            while (true) {
                unsigned bad = 0;
#pragma unroll
                for (int i = 0; i < 7; i++) w[i] = ld_rlx(hp + i * 32);
#pragma unroll
                for (int i = 0; i < 7; i++) bad |= tag_bad(w[i], tag);
                if (!__any_sync(~0u, bad)) break;
                spin_check(n);
                __nanosleep(200);
            }
#pragma unroll
            for (int i = 0; i < 7; i++) sts32(hd + i * 128, bf_bits(untag(w[i])));
            mbar_arrive(bar_hs);
        }
        {
            mbar_wait(bar_ml, 0);
            const uint2 ml = lds64(sb + SM_ML + (lane & 7) * 8);
            float M = as_f(ml.x);
#pragma unroll
            for (int o = 4; o > 0; o >>= 1) M = fmaxf(M, __shfl_xor_sync(~0u, M, o));
            M = untag(__float_as_uint(M));
            float L = as_f(ml.y) * ex2((as_f(ml.x) - M) * SM_SCALE);
#pragma unroll
            for (int o = 4; o > 0; o >>= 1) L += __shfl_xor_sync(~0u, L, o);
            unsigned* sp = scr + G_ST + (h * 2 + b) * 32;
            if (lane < 8) st_rlx(sp + s * 8 + lane, tagw((lane & 1) ? L : M, tag));
            uint2 w; unsigned n = 0;
            while (true) {
                w = ld_rlx2(sp + (lane & 3) * 8);
                if (!__any_sync(~0u, tag_bad(w.x, tag) | tag_bad(w.y, tag))) break;
                spin_check(n);
                __nanosleep(200);
            }
            const float ms = untag(w.x);
            float M2 = fmaxf(ms, __shfl_xor_sync(~0u, ms, 1));
            M2 = fmaxf(M2, __shfl_xor_sync(~0u, M2, 2));
            float L2 = untag(w.y) * ex2((ms - M2) * SM_SCALE);
            L2 += __shfl_xor_sync(~0u, L2, 1);
            L2 += __shfl_xor_sync(~0u, L2, 2);
            if (lane < NW) {
                sts32(sb + SM_FAC + lane * 4, __float_as_uint((b ? g1 : g0) * ex2((as_f(ml.x) - M2) * SM_SCALE) * rcp(L2)));
                mbar_arrive(bar_fac);
            }
        }
        if (c < 112) {
            const unsigned* op = scr + G_O2 + (c * NH + 4 * (lane >> 3)) * 8 + (lane & 7);
            unsigned w0, w1, w2, w3, n = 0;
            while (true) {
                w0 = ld_rlx(op); w1 = ld_rlx(op + 8); w2 = ld_rlx(op + 16); w3 = ld_rlx(op + 24);
                if (!__any_sync(~0u, tag_bad(w0, tag) | tag_bad(w1, tag) | tag_bad(w2, tag) | tag_bad(w3, tag))) break;
                spin_check(n);
            }
            float a = (untag(w0) + untag(w1)) + (untag(w2) + untag(w3));
            a += __shfl_xor_sync(~0u, a, 8);
            a += __shfl_xor_sync(~0u, a, 16);
            if (lane < 8) out[(c / 56) * DM + 8 * (c % 56) + lane] = __float2bfloat16_rn(a);
            if (c == 0 && lane == 0) st_rlx(scr + G_STATE, tag);
        }
    }
}

}

typedef CUresult (*EncodeTiledFn)(CUtensorMap*, CUtensorMapDataType, cuuint32_t, void*, const cuuint64_t*, const cuuint64_t*,
                                  const cuuint32_t*, const cuuint32_t*, CUtensorMapInterleave, CUtensorMapSwizzle,
                                  CUtensorMapL2promotion, CUtensorMapFloatOOBfill);

static CUtensorMap make_map(EncodeTiledFn enc, const void* base, int cols, int rows, int box_cols, int box_rows,
                            CUtensorMapSwizzle swz) {
    CUtensorMap m;
    const cuuint64_t dims[2] = {(cuuint64_t)cols, (cuuint64_t)rows};
    const cuuint64_t strides[1] = {(cuuint64_t)cols * 2};
    const cuuint32_t box[2] = {(cuuint32_t)box_cols, (cuuint32_t)box_rows};
    const cuuint32_t estr[2] = {1, 1};
    enc(&m, CU_TENSOR_MAP_DATA_TYPE_BFLOAT16, 2, const_cast<void*>(base), dims, strides, box, estr, CU_TENSOR_MAP_INTERLEAVE_NONE,
        swz, CU_TENSOR_MAP_L2_PROMOTION_NONE, CU_TENSOR_MAP_FLOAT_OOB_FILL_NONE);
    return m;
}

extern "C" void kernel_launch(void* const* d_in, const int* in_sizes, int n_in, void* d_out, int out_size) {
    (void)in_sizes; (void)n_in; (void)out_size;
    static EncodeTiledFn enc = nullptr;
    static int pace_t0 = 0, pace_stag = 0, pace_tau = 0, pace_del = 0;
    if (!enc) {
        cudaFuncSetAttribute(fused_decode_kernel, cudaFuncAttributeMaxDynamicSharedMemorySize, SM_TOTAL);
        void* fn = nullptr;
        cudaDriverEntryPointQueryResult qr;
        cudaGetDriverEntryPoint("cuTensorMapEncodeTiled", &fn, cudaEnableDefault, &qr);
        enc = (EncodeTiledFn)fn;
        int dev = 0, khz = 0, bits = 0;
        cudaGetDevice(&dev);
        cudaDeviceGetAttribute(&khz, cudaDevAttrMemoryClockRate, dev);
        cudaDeviceGetAttribute(&bits, cudaDevAttrGlobalMemoryBusWidth, dev);
        const double scale = khz > 0 && bits > 0 ? (2619000.0 * 5120.0) / ((double)khz * bits) : 0.0;
        if (scale > 0.5 && scale < 2.5) {
            pace_t0 = (int)(PACE_T0 * scale); pace_stag = (int)(PACE_STAG * scale);
            pace_tau = (int)(PACE_TAU * scale); pace_del = (int)(PACE_DEL * scale);
        }
    }
    const __nv_bfloat16* x  = (const __nv_bfloat16*)d_in[0];
    const __nv_bfloat16* Kc = (const __nv_bfloat16*)d_in[1];
    const __nv_bfloat16* Vc = (const __nv_bfloat16*)d_in[2];
    const __nv_bfloat16* wq = (const __nv_bfloat16*)d_in[3];
    const __nv_bfloat16* gw = (const __nv_bfloat16*)d_in[9];
    const CUtensorMap tm_wo = make_map(enc, d_in[4], DM, NH * DH, 64, 32, CU_TENSOR_MAP_SWIZZLE_128B);
    const CUtensorMap tm_wg = make_map(enc, d_in[6], DFF, DM, 16, 224, CU_TENSOR_MAP_SWIZZLE_NONE);
    const CUtensorMap tm_wu = make_map(enc, d_in[7], DFF, DM, 16, 224, CU_TENSOR_MAP_SWIZZLE_NONE);
    const CUtensorMap tm_wd = make_map(enc, d_in[8], DM, DFF, 64, 112, CU_TENSOR_MAP_SWIZZLE_128B);
    fused_decode_kernel<<<NCTA, NTHREADS, SM_TOTAL, cudaStreamPerThread>>>(x, Kc, Vc, wq, gw, (__nv_bfloat16*)d_out, tm_wg, tm_wu, tm_wd, tm_wo,
                                                                          pace_t0, pace_stag, pace_tau, pace_del);
}
```
